```python
import torch

def _softmax(x, axis=-1):
    return torch.softmax(x, dim=axis)

def _gelu(x):
    return torch.nn.functional.gelu(x, approximate='tanh')

def _silu(x):
    return torch.nn.functional.silu(x)

def _sigmoid(x):
    return torch.sigmoid(x)

def _layernorm(x, axis=-1, eps=1e-05):
    m = x.mean(dim=axis, keepdim=True)
    v = x.var(dim=axis, keepdim=True, unbiased=False)
    return (x - m) / torch.sqrt(v + eps)

def _scatter_add(tgt, idx, src, axis=0):
    return tgt.clone().index_add_(axis, idx, src)

def _segment_sum(src, seg, n):
    out = torch.zeros((n,) + src.shape[1:], dtype=src.dtype)
    return out.index_add_(0, seg, src)

def _pad(x, pw):
    flat = tuple((v for pair in reversed(pw) for v in pair))
    return torch.nn.functional.pad(x, flat)
kernel_name = 'standalone__factorization_afm__recsys'

def setup_inputs():

    _w = lambda a: (lambda t: t.to(torch.bfloat16) if t.is_floating_point() else t)(torch.as_tensor(a))
    B, F, D, V = (4096, 26, 128, min(1000, 100000))
    A = D
    ii, jj = tuple(torch.triu_indices(F, F, 1).unbind(0))
    return {'idx': _w((lambda lo, hi, *s: torch.randint(lo, hi, s))(0, V, B, F).to(torch.int64)), 'table': _w((lambda *s: torch.randn(*s, dtype=torch.bfloat16) * 0.2)(V, D)), 'ii': _w(ii.to(torch.int64)), 'jj': _w(jj.to(torch.int64)), 'W': _w((lambda *s: torch.randn(*s, dtype=torch.bfloat16) * 1.6)(D, A) * (1.0 / D ** 0.5)), 'b': _w((lambda *s: torch.randn(*s, dtype=torch.bfloat16) * 1.6)(A)), 'h': _w((lambda *s: torch.randn(*s, dtype=torch.bfloat16) * 1.6)(A)), 'p': _w((lambda *s: torch.randn(*s, dtype=torch.bfloat16) * 0.2)(D))}

def reference(idx, table, ii, jj, W, b, h, p):
    emb = table[idx]
    ei = emb[:, ii, :].clone()
    ej = emb[:, jj, :].clone()
    pair = ei * ej
    hid = pair @ W + b
    hid = 0.5 * (hid + torch.abs(hid))
    e = hid @ h
    alpha = _softmax(e, axis=-1)
    pooled = torch.einsum('bp,bpd->bd', alpha, pair)
    return pooled @ p
```

```cpp
#include <cuda_runtime.h>
#include <cuda_bf16.h>
#include <stdint.h>

namespace {

constexpr int kV = 1000, kD = 128, kB = 4096, kF = 26, kP = 325;
constexpr int kSlabs = kV / 8;
constexpr int kUPS = 504;
constexpr int kUnits = kSlabs * kUPS;
constexpr int kSteps = 30;
constexpr int kSlots = 16;
constexpr int kUPC = kSteps * kSlots;
constexpr int kCTAs = 132;
constexpr int kSamplesPerCTA = 32;
constexpr int kLookups = kSamplesPerCTA * kP;
constexpr int kThreads = 384;

constexpr int kNumStages = 4;
__host__ __device__ constexpr int stage_end(int s) { return s == 0 ? 12 : s == 1 ? 22 : s == 2 ? 28 : 30; }
__host__ __device__ constexpr int stage_begin(int s) { return s == 0 ? 0 : stage_end(s - 1); }
constexpr int kNumTuGroups = 4;
__host__ __device__ constexpr int tu_end(int g) { return g == 0 ? 2 : g == 1 ? 8 : g == 2 ? 16 : 30; }
__host__ __device__ constexpr int tu_begin(int g) { return g == 0 ? 0 : tu_end(g - 1); }

constexpr uint32_t kPendMark = 0xFFC00000u;

constexpr int SM_W = 0;
constexpr int SM_TU = SM_W + 32768;
constexpr int SM_TV = SM_TU + kUPC * 256;
constexpr int SM_ES = SM_TV + 16 * 256;
constexpr int SM_LK = SM_ES + kUPC * 32;
constexpr int SM_IDX = SM_LK + kLookups * 4;
constexpr int SM_IJ = SM_IDX + kSamplesPerCTA * kF * 4;
constexpr int SM_P = SM_IJ + 656;
constexpr int SM_BAR = SM_P + 256;
constexpr int SM_TOTAL = SM_BAR + 128;
static_assert(SM_TOTAL + 1024 <= 232448, "smem");
static_assert(SM_P % 16 == 0 && SM_BAR % 8 == 0 && SM_LK % 16 == 0 && SM_IDX % 16 == 0, "align");

constexpr int BAR_TU = 0;
constexpr int BAR_STAGE = BAR_TU + kNumTuGroups;
constexpr int BAR_GO = BAR_STAGE + kNumStages;
constexpr int BAR_GDONE = BAR_GO + kNumStages;
constexpr int BAR_COUNT = BAR_GDONE + 1;
static_assert(BAR_COUNT * 8 <= 128, "bars");

constexpr uint32_t kSpinLimit = 1u << 22;

__device__ uint32_t g_table[kUnits * 8 + 64];
__device__ uint32_t g_cnt[kNumStages * 32];
__device__ uint32_t g_epoch;
#define TSTAMP(i) do { } while (0)

__device__ __forceinline__ uint32_t smem_u32(const void* p) { return (uint32_t)__cvta_generic_to_shared(p); }

__device__ __forceinline__ void mbar_init(uint32_t bar, uint32_t cnt) {
    asm volatile("mbarrier.init.shared::cta.b64 [%0], %1;" ::"r"(bar), "r"(cnt) : "memory");
}
__device__ __forceinline__ void mbar_arrive(uint32_t bar) {
    asm volatile("mbarrier.arrive.shared::cta.b64 _, [%0];" ::"r"(bar) : "memory");
}
__device__ __forceinline__ void mbar_expect_tx(uint32_t bar, uint32_t bytes) {
    asm volatile("mbarrier.arrive.expect_tx.shared::cta.b64 _, [%0], %1;" ::"r"(bar), "r"(bytes) : "memory");
}
__device__ __forceinline__ bool mbar_try(uint32_t bar, uint32_t parity) {
    uint32_t ok;
    asm volatile("{\n\t.reg .pred p;\n\tmbarrier.try_wait.parity.shared::cta.b64 p, [%1], %2;\n\tselp.u32 %0, 1, 0, p;\n\t}"
                 : "=r"(ok) : "r"(bar), "r"(parity) : "memory");
    return ok != 0;
}
__device__ __forceinline__ void mbar_wait(uint32_t bar, uint32_t parity) {
    uint32_t n = 0;
    while (!mbar_try(bar, parity)) {
        if (++n > kSpinLimit) __trap();
    }
}
__device__ __forceinline__ void bulk_g2s(uint32_t dst, const void* src, uint32_t bytes, uint32_t bar) {
    asm volatile("cp.async.bulk.shared::cluster.global.mbarrier::complete_tx::bytes [%0], [%1], %2, [%3];"
                 ::"r"(dst), "l"(src), "r"(bytes), "r"(bar) : "memory");
}
__device__ __forceinline__ void cp_async16(uint32_t dst, const void* src) {
    asm volatile("cp.async.cg.shared.global [%0], [%1], 16;" ::"r"(dst), "l"(src) : "memory");
}
__device__ __forceinline__ uint4 lds128(uint32_t a) {
    uint4 v;
    asm volatile("ld.shared.v4.u32 {%0,%1,%2,%3}, [%4];" : "=r"(v.x), "=r"(v.y), "=r"(v.z), "=r"(v.w) : "r"(a));
    return v;
}
__device__ __forceinline__ uint32_t lds32(uint32_t a) {
    uint32_t v;
    asm volatile("ld.shared.u32 %0, [%1];" : "=r"(v) : "r"(a));
    return v;
}
__device__ __forceinline__ void sts32(uint32_t a, uint32_t v) { asm volatile("st.shared.u32 [%0], %1;" ::"r"(a), "r"(v) : "memory"); }
__device__ __forceinline__ void sts16(uint32_t a, uint16_t v) { asm volatile("st.shared.u16 [%0], %1;" ::"r"(a), "h"(v) : "memory"); }
__device__ __forceinline__ uint32_t bmul2(uint32_t a, uint32_t b) {
    uint32_t d;
    asm("mul.rn.bf16x2 %0, %1, %2;" : "=r"(d) : "r"(a), "r"(b));
    return d;
}
__device__ __forceinline__ uint32_t pack_bf16x2(float hi, float lo) {
    uint32_t d;
    asm("cvt.rn.bf16x2.f32 %0, %1, %2;" : "=r"(d) : "f"(hi), "f"(lo));
    return d;
}
__device__ __forceinline__ uint32_t add_relu_bf16x2(uint32_t x, uint32_t b) {
    uint32_t d;
    asm("fma.rn.relu.bf16x2 %0, %1, %2, %3;" : "=r"(d) : "r"(x), "r"(0x3F803F80u), "r"(b));
    return d;
}
__device__ __forceinline__ uint16_t cvt_bf16(float x) {
    uint16_t d;
    asm("cvt.rn.bf16.f32 %0, %1;" : "=h"(d) : "f"(x));
    return d;
}
__device__ __forceinline__ void named_sync(int id, int n) { asm volatile("bar.sync %0, %1;" ::"r"(id), "r"(n) : "memory"); }
__device__ __forceinline__ void named_arrive(int id, int n) { asm volatile("bar.arrive %0, %1;" ::"r"(id), "r"(n) : "memory"); }

__device__ __forceinline__ void wgmma_m64n128k16(float (&d)[64], uint32_t a0, uint32_t a1, uint32_t a2, uint32_t a3,
                                                 uint64_t desc, int scale_d) {
    asm volatile(
        "{\n\t.reg .pred p;\n\tsetp.ne.b32 p, %69, 0;\n\t"
        "wgmma.mma_async.sync.aligned.m64n128k16.f32.bf16.bf16 "
        "{%0,%1,%2,%3,%4,%5,%6,%7,%8,%9,%10,%11,%12,%13,%14,%15,"
        "%16,%17,%18,%19,%20,%21,%22,%23,%24,%25,%26,%27,%28,%29,%30,%31,"
        "%32,%33,%34,%35,%36,%37,%38,%39,%40,%41,%42,%43,%44,%45,%46,%47,"
        "%48,%49,%50,%51,%52,%53,%54,%55,%56,%57,%58,%59,%60,%61,%62,%63},"
        "{%64,%65,%66,%67}, %68, p, 1, 1, 1;\n\t}"
        : "+f"(d[0]), "+f"(d[1]), "+f"(d[2]), "+f"(d[3]), "+f"(d[4]), "+f"(d[5]), "+f"(d[6]), "+f"(d[7]),
          "+f"(d[8]), "+f"(d[9]), "+f"(d[10]), "+f"(d[11]), "+f"(d[12]), "+f"(d[13]), "+f"(d[14]), "+f"(d[15]),
          "+f"(d[16]), "+f"(d[17]), "+f"(d[18]), "+f"(d[19]), "+f"(d[20]), "+f"(d[21]), "+f"(d[22]), "+f"(d[23]),
          "+f"(d[24]), "+f"(d[25]), "+f"(d[26]), "+f"(d[27]), "+f"(d[28]), "+f"(d[29]), "+f"(d[30]), "+f"(d[31]),
          "+f"(d[32]), "+f"(d[33]), "+f"(d[34]), "+f"(d[35]), "+f"(d[36]), "+f"(d[37]), "+f"(d[38]), "+f"(d[39]),
          "+f"(d[40]), "+f"(d[41]), "+f"(d[42]), "+f"(d[43]), "+f"(d[44]), "+f"(d[45]), "+f"(d[46]), "+f"(d[47]),
          "+f"(d[48]), "+f"(d[49]), "+f"(d[50]), "+f"(d[51]), "+f"(d[52]), "+f"(d[53]), "+f"(d[54]), "+f"(d[55]),
          "+f"(d[56]), "+f"(d[57]), "+f"(d[58]), "+f"(d[59]), "+f"(d[60]), "+f"(d[61]), "+f"(d[62]), "+f"(d[63])
        : "r"(a0), "r"(a1), "r"(a2), "r"(a3), "l"(desc), "r"(scale_d));
}
__device__ __forceinline__ void mma16816(float (&d)[4], uint32_t a0, uint32_t a1, uint32_t a2, uint32_t a3,
                                         uint32_t b0, uint32_t b1) {
    asm volatile("mma.sync.aligned.m16n8k16.row.col.f32.bf16.bf16.f32 {%0,%1,%2,%3}, {%4,%5,%6,%7}, {%8,%9}, {%0,%1,%2,%3};"
                 : "+f"(d[0]), "+f"(d[1]), "+f"(d[2]), "+f"(d[3])
                 : "r"(a0), "r"(a1), "r"(a2), "r"(a3), "r"(b0), "r"(b1));
}

__device__ __forceinline__ int unit_u(int n) {
    n = min(n, kUnits - 1);
    int J = n / kUPS;
    int u = 8 * J + (n - J * kUPS);
    return u >= kV ? u - kV : u;
}

__global__ void __launch_bounds__(kThreads, 1)
afm_kernel(const int* __restrict__ idx, const __nv_bfloat16* __restrict__ table, const int* __restrict__ ii,
           const int* __restrict__ jj, const __nv_bfloat16* __restrict__ W, const __nv_bfloat16* __restrict__ bias,
           const __nv_bfloat16* __restrict__ hvec, const __nv_bfloat16* __restrict__ pvec,
           __nv_bfloat16* __restrict__ out) {
    extern __shared__ uint8_t smem_raw[];
    const uint32_t sb = (smem_u32(smem_raw) + 1023u) & ~1023u;
    const int tid = threadIdx.x, warp = tid >> 5, lane = tid & 31;
    const int g = lane >> 2, q = lane & 3;
    const int cta = blockIdx.x;
    const int n0 = cta * kUPC;
    const int JA = n0 / kUPS;
    const int nc = (JA + 1) * kUPS - n0;
    const uint32_t bars = sb + SM_BAR;

    if (warp == 11) {
        if (lane == 0) {
            for (int i = 0; i < kNumTuGroups; i++) mbar_init(bars + 8 * (BAR_TU + i), 1);
            for (int i = 0; i < kNumStages; i++) mbar_init(bars + 8 * (BAR_STAGE + i), i == 0 ? 11 : 8);
            for (int i = 0; i < kNumStages; i++) mbar_init(bars + 8 * (BAR_GO + i), 1);
            mbar_init(bars + 8 * BAR_GDONE, 3);
            asm volatile("fence.mbarrier_init.release.cluster;" ::: "memory");
            asm volatile("fence.proxy.async.shared::cta;" ::: "memory");
            mbar_expect_tx(bars + 8 * (BAR_TU + 0), tu_end(0) * kSlots * 256 + 4096 + 256);
            for (int i = 1; i < kNumTuGroups; i++)
                mbar_expect_tx(bars + 8 * (BAR_TU + i), (tu_end(i) - tu_begin(i)) * kSlots * 256);
            const int JB = min(JA + 1, kSlabs - 1);
            bulk_g2s(sb + SM_TV, table + (size_t)JA * 8 * kD, 2048, bars + 8 * BAR_TU);
            bulk_g2s(sb + SM_TV + 2048, table + (size_t)JB * 8 * kD, 2048, bars + 8 * BAR_TU);
            bulk_g2s(sb + SM_P, pvec, 256, bars + 8 * BAR_TU);
        }
        __syncwarp();
        const int slot = lane & 15;
#pragma unroll
        for (int t2 = 0; t2 < kSteps / 2; t2++) {
            const int t = 2 * t2 + (lane >> 4);
            const int grp = 2 * t2 < tu_end(0) ? 0 : 2 * t2 < tu_end(1) ? 1 : 2 * t2 < tu_end(2) ? 2 : 3;
            const int r = slot * kSteps + t;
            bulk_g2s(sb + SM_TU + r * 256, table + (size_t)unit_u(n0 + r) * kD, 256, bars + 8 * (BAR_TU + grp));
        }
    } else if (warp < 8) {
#pragma unroll
        for (int i = 0; i < 8; i++) {
            const int ch = tid + 256 * i;
            const int d = ch >> 4, cc = ch & 15;
            const int kap = (d & ~31) + ((d >> 2) & 1) * 16 + ((d >> 1) & 1) * 8 + ((d >> 3) & 3) * 2 + (d & 1);
            const uint32_t dst = sb + SM_W + (cc >> 3) * 16384 + (kap >> 3) * 1024 + (kap & 7) * 128 + (((cc & 7) ^ (kap & 7)) << 4);
            cp_async16(dst, W + d * kD + cc * 8);
        }
        asm volatile("cp.async.commit_group;" ::: "memory");
    }
    __syncthreads();

    if (warp < 8) {
        asm volatile("setmaxnreg.inc.sync.aligned.u32 224;");
        const int wg = warp >> 2;
        uint32_t bpk[16];
        float hf[32];
#pragma unroll
        for (int j = 0; j < 16; j++) {
            bpk[j] = __ldg(reinterpret_cast<const uint32_t*>(bias) + 4 * j + q);
            const uint32_t hh = __ldg(reinterpret_cast<const uint32_t*>(hvec) + 4 * j + q);
            hf[2 * j] = __uint_as_float(hh << 16);
            hf[2 * j + 1] = __uint_as_float(hh & 0xFFFF0000u);
        }
        const int ns0 = 2 * warp * kSteps, ns1 = ns0 + kSteps;
        const int tc0 = nc - ns0, tc1 = nc - ns1;
        uint32_t tv0[16], tv1[16];
        asm volatile("cp.async.wait_group 0;" ::: "memory");
        asm volatile("fence.proxy.async.shared::cta;" ::: "memory");
        mbar_wait(bars + 8 * BAR_TU, 0);
        {
            const uint32_t a0 = sb + SM_TV + (tc0 <= 0 ? 2048 : 0) + g * 256 + q * 16;
            const uint32_t a1 = sb + SM_TV + (tc1 <= 0 ? 2048 : 0) + g * 256 + q * 16;
#pragma unroll
            for (int j = 0; j < 4; j++) {
                uint4 v = lds128(a0 + 64 * j);
                tv0[4 * j] = v.x; tv0[4 * j + 1] = v.y; tv0[4 * j + 2] = v.z; tv0[4 * j + 3] = v.w;
                v = lds128(a1 + 64 * j);
                tv1[4 * j] = v.x; tv1[4 * j + 1] = v.y; tv1[4 * j + 2] = v.z; tv1[4 * j + 3] = v.w;
            }
        }
        named_sync(1, 256);
        if (tid == 0) TSTAMP(1);
        if (wg == 1) named_arrive(2, 256);
        const uint64_t desc0 = (uint64_t)(((sb + SM_W) & 0x3FFFF) >> 4) | ((uint64_t)(16384 >> 4) << 16) |
                               ((uint64_t)(1024 >> 4) << 32) | (1ull << 62);
        uint32_t tu_addr = sb + SM_TU + ns0 * 256 + q * 16;
        uint32_t es_addr = sb + SM_ES + (ns0 + (q >> 1) * kSteps) * 32 + g * 4;
        float acc[64];
#pragma unroll 1
        for (int t = 0; t < kSteps; t++) {
            if (t == tu_end(0)) mbar_wait(bars + 8 * (BAR_TU + 1), 0);
            if (t == tu_end(1)) mbar_wait(bars + 8 * (BAR_TU + 2), 0);
            if (t == tu_end(2)) mbar_wait(bars + 8 * (BAR_TU + 3), 0);
            if (t == tc0) {
#pragma unroll
                for (int j = 0; j < 4; j++) {
                    uint4 v = lds128(sb + SM_TV + 2048 + g * 256 + q * 16 + 64 * j);
                    tv0[4 * j] = v.x; tv0[4 * j + 1] = v.y; tv0[4 * j + 2] = v.z; tv0[4 * j + 3] = v.w;
                }
            }
            if (t == tc1) {
#pragma unroll
                for (int j = 0; j < 4; j++) {
                    uint4 v = lds128(sb + SM_TV + 2048 + g * 256 + q * 16 + 64 * j);
                    tv1[4 * j] = v.x; tv1[4 * j + 1] = v.y; tv1[4 * j + 2] = v.z; tv1[4 * j + 3] = v.w;
                }
            }
            uint32_t a[32];
#pragma unroll
            for (int j = 0; j < 4; j++) {
                const uint4 u0 = lds128(tu_addr + 64 * j);
                const uint4 u1 = lds128(tu_addr + kSteps * 256 + 64 * j);
                a[8 * j + 0] = bmul2(tv0[4 * j + 0], u0.x);
                a[8 * j + 1] = bmul2(tv1[4 * j + 0], u1.x);
                a[8 * j + 2] = bmul2(tv0[4 * j + 1], u0.y);
                a[8 * j + 3] = bmul2(tv1[4 * j + 1], u1.y);
                a[8 * j + 4] = bmul2(tv0[4 * j + 2], u0.z);
                a[8 * j + 5] = bmul2(tv1[4 * j + 2], u1.z);
                a[8 * j + 6] = bmul2(tv0[4 * j + 3], u0.w);
                a[8 * j + 7] = bmul2(tv1[4 * j + 3], u1.w);
            }
            tu_addr += 256;
            named_sync(2 + wg, 256);
            asm volatile("wgmma.fence.sync.aligned;" ::: "memory");
#pragma unroll
            for (int s = 0; s < 8; s++)
                wgmma_m64n128k16(acc, a[4 * s], a[4 * s + 1], a[4 * s + 2], a[4 * s + 3], desc0 + (uint64_t)(s * 128), s);
            asm volatile("wgmma.commit_group.sync.aligned;" ::: "memory");
            if (wg == 0 || t + 1 < kSteps) named_arrive(3 - wg, 256);
            asm volatile("wgmma.wait_group.sync.aligned 0;" ::: "memory");
#pragma unroll
            for (int i = 0; i < 64; i++) asm volatile("" : "+f"(acc[i])::"memory");
            float e0a = 0.f, e0b = 0.f, e1a = 0.f, e1b = 0.f;
#pragma unroll
            for (int j = 0; j < 16; j++) {
                const uint32_t r0 = add_relu_bf16x2(pack_bf16x2(acc[4 * j + 1], acc[4 * j]), bpk[j]);
                const uint32_t r1 = add_relu_bf16x2(pack_bf16x2(acc[4 * j + 3], acc[4 * j + 2]), bpk[j]);
                e0a = fmaf(__uint_as_float(r0 << 16), hf[2 * j], e0a);
                e0b = fmaf(__uint_as_float(r0 & 0xFFFF0000u), hf[2 * j + 1], e0b);
                e1a = fmaf(__uint_as_float(r1 << 16), hf[2 * j], e1a);
                e1b = fmaf(__uint_as_float(r1 & 0xFFFF0000u), hf[2 * j + 1], e1b);
            }
            const float e0 = e0a + e0b, e1 = e1a + e1b;
            float mine = (q & 2) ? e1 : e0;
            const float other = (q & 2) ? e0 : e1;
            mine += __shfl_xor_sync(0xffffffffu, other, 2);
            mine += __shfl_xor_sync(0xffffffffu, mine, 1);
            if (!(q & 1)) sts16(es_addr, cvt_bf16(mine));
            es_addr += 32;
#pragma unroll
            for (int s = 0; s < kNumStages; s++) {
                if (t + 1 == stage_end(s)) {
                    __syncwarp();
                    if (lane == 0) mbar_arrive(bars + 8 * (BAR_STAGE + s));
                    if (tid == 0) TSTAMP(2 + s);
                }
            }
        }
        if (cta < kB / kSamplesPerCTA) {
            mbar_wait(bars + 8 * BAR_GDONE, 0);
            uint32_t val[4][11];
#pragma unroll
            for (int sidx = 0; sidx < 4; sidx++)
#pragma unroll
                for (int i = 0; i < 11; i++) {
                    const int p = lane + 32 * i;
                    val[sidx][i] = (i < 10 || lane < kP - 320) ? lds32(sb + SM_LK + ((warp * 4 + sidx) * kP + p) * 4) : 0x0000FF80u;
                }
            if (tid == 0) TSTAMP(6);
            mbar_wait(bars + 8 * (BAR_GO + kNumStages - 1), 0);
            if (tid == 0) TSTAMP(7);
#pragma unroll
            for (int sidx = 0; sidx < 4; sidx++)
#pragma unroll
                for (int i = 0; i < 11; i++) {
                    if (val[sidx][i] >= kPendMark)
                        asm volatile("ld.relaxed.gpu.global.u32 %0, [%1];" : "=r"(val[sidx][i])
                                     : "l"(g_table + (val[sidx][i] & 0x7FFFFu)) : "memory");
                }
#pragma unroll
            for (int sidx = 0; sidx < 4; sidx++) {
                float m = -INFINITY;
#pragma unroll
                for (int i = 0; i < 11; i++) m = fmaxf(m, __uint_as_float(val[sidx][i] << 16));
#pragma unroll
                for (int o = 16; o > 0; o >>= 1) m = fmaxf(m, __shfl_xor_sync(0xffffffffu, m, o));
                float l = 0.f, a = 0.f;
#pragma unroll
                for (int i = 0; i < 11; i++) {
                    const float w = __expf(__uint_as_float(val[sidx][i] << 16) - m);
                    l += w;
                    a = fmaf(w, __uint_as_float(val[sidx][i] & 0xFFFF0000u), a);
                }
#pragma unroll
                for (int o = 16; o > 0; o >>= 1) {
                    l += __shfl_xor_sync(0xffffffffu, l, o);
                    a += __shfl_xor_sync(0xffffffffu, a, o);
                }
                if (lane == 0) out[cta * kSamplesPerCTA + warp * 4 + sidx] = __float2bfloat16(a / l);
            }
            if (tid == 0) TSTAMP(8);
        }
    } else {
        asm volatile("setmaxnreg.dec.sync.aligned.u32 56;");
        if (warp == 11) {
            uint32_t target;
            asm volatile("ld.relaxed.gpu.global.u32 %0, [%1];" : "=r"(target) : "l"(&g_epoch) : "memory");
            const uint32_t epoch = target;
            target = (target + 1) * kCTAs;
#pragma unroll 1
            for (int s = 0; s < kNumStages; s++) {
                const int t0 = s == 0 ? 0 : s == 1 ? stage_end(0) : s == 2 ? stage_end(1) : stage_end(2);
                const int t1 = s == 0 ? stage_end(0) : s == 1 ? stage_end(1) : s == 2 ? stage_end(2) : stage_end(3);
                mbar_wait(bars + 8 * (BAR_STAGE + s), 0);
                const int slot = lane >> 1;
                for (int t = t0; t < t1; t++) {
                    const int r = slot * kSteps + t;
                    const uint4 v = lds128(sb + SM_ES + r * 32 + (lane & 1) * 16);
                    if (n0 + r < kUnits) *reinterpret_cast<uint4*>(g_table + (size_t)(n0 + r) * 8 + (lane & 1) * 4) = v;
                }
                __syncwarp();
                if (lane == 0) {
                    asm volatile("red.release.gpu.global.add.u32 [%0], 1;" ::"l"(g_cnt + 32 * s) : "memory");
                    TSTAMP(10 + s);
                    uint32_t c, n = 0;
                    do {
                        asm volatile("ld.acquire.gpu.global.u32 %0, [%1];" : "=r"(c) : "l"(g_cnt + 32 * s) : "memory");
                        if (++n > kSpinLimit) __trap();
                    } while ((int)(c - target) < 0);
                    mbar_arrive(bars + 8 * (BAR_GO + s));
                    TSTAMP(14 + s);
                }
                __syncwarp();
            }
            if (cta == 0 && lane == 0) asm volatile("st.relaxed.gpu.global.u32 [%0], %1;" ::"l"(&g_epoch), "r"(epoch + 1) : "memory");
        } else {
            const int ht = tid - 256;
            const int hw = warp - 8;
            const bool has_samples = cta < kB / kSamplesPerCTA;
            if (has_samples) {
                for (int i = ht; i < kSamplesPerCTA * kF; i += 96)
                    sts32(sb + SM_IDX + i * 4, (uint32_t)__ldg(idx + cta * kSamplesPerCTA * kF + i));
                for (int i = ht; i < kP; i += 96)
                    sts16(sb + SM_IJ + i * 2, (uint16_t)(__ldg(ii + i) * 4 | (__ldg(jj + i) * 4) << 8));
                named_sync(4, 96);
#pragma unroll 1
                for (int p = ht; p < kP + 59; p += 96) {
                    if (p < kP) {
                        uint16_t ij;
                        asm volatile("ld.shared.u16 %0, [%1];" : "=h"(ij) : "r"(sb + SM_IJ + p * 2));
                        const uint32_t oi = sb + SM_IDX + (ij & 0xFF), oj = sb + SM_IDX + (ij >> 8);
#pragma unroll 4
                        for (int sm = 0; sm < kSamplesPerCTA; sm++) {
                            int x = (int)lds32(oi + sm * (kF * 4)), y = (int)lds32(oj + sm * (kF * 4));
                            int dd = (y >> 3) - (x >> 3);
                            if (dd < 0) dd += kSlabs;
                            if (dd > 62) { dd = kSlabs - dd; const int tmp = x; x = y; y = tmp; }
                            const uint32_t n = (uint32_t)((x >> 3) * kUPS + 8 * dd + (y & 7));
                            const uint32_t step = n % kSteps;
                            const uint32_t st = (step >= stage_end(0)) + (step >= stage_end(1)) + (step >= stage_end(2));
                            sts32(sb + SM_LK + (sm * kP + p) * 4, kPendMark | (st << 19) | (n * 8 + (x & 7)));
                        }
                    }
                }
            }
            if (ht == 0) TSTAMP(20);
            mbar_wait(bars + 8 * (BAR_TU + 0), 0);
            mbar_wait(bars + 8 * (BAR_TU + 1), 0);
            mbar_wait(bars + 8 * (BAR_TU + 2), 0);
            mbar_wait(bars + 8 * (BAR_TU + 3), 0);
#pragma unroll 1
            for (int blk = hw; blk < kUPC / 16; blk += 3) {
                const int r0 = blk * 16 + g, r1 = r0 + 8;
                const bool use_a = blk * 16 < nc, use_b = blk * 16 + 15 >= nc;
                float sa[4] = {0.f, 0.f, 0.f, 0.f}, sbv[4] = {0.f, 0.f, 0.f, 0.f};
#pragma unroll
                for (int j = 0; j < 4; j++) {
                    const uint4 pp = lds128(sb + SM_P + q * 16 + 64 * j);
                    const uint4 u0 = lds128(sb + SM_TU + r0 * 256 + q * 16 + 64 * j);
                    const uint4 u1 = lds128(sb + SM_TU + r1 * 256 + q * 16 + 64 * j);
                    const uint32_t a0 = bmul2(u0.x, pp.x), a1 = bmul2(u1.x, pp.x), a2 = bmul2(u0.y, pp.y), a3 = bmul2(u1.y, pp.y);
                    const uint32_t a4 = bmul2(u0.z, pp.z), a5 = bmul2(u1.z, pp.z), a6 = bmul2(u0.w, pp.w), a7 = bmul2(u1.w, pp.w);
                    if (use_a) {
                        const uint4 tv = lds128(sb + SM_TV + g * 256 + q * 16 + 64 * j);
                        mma16816(sa, a0, a1, a2, a3, tv.x, tv.y);
                        mma16816(sa, a4, a5, a6, a7, tv.z, tv.w);
                    }
                    if (use_b) {
                        const uint4 tv = lds128(sb + SM_TV + 2048 + g * 256 + q * 16 + 64 * j);
                        mma16816(sbv, a0, a1, a2, a3, tv.x, tv.y);
                        mma16816(sbv, a4, a5, a6, a7, tv.z, tv.w);
                    }
                }
                const bool b0 = r0 >= nc, b1 = r1 >= nc;
                sts16(sb + SM_ES + r0 * 32 + q * 8 + 2, cvt_bf16(b0 ? sbv[0] : sa[0]));
                sts16(sb + SM_ES + r0 * 32 + q * 8 + 6, cvt_bf16(b0 ? sbv[1] : sa[1]));
                sts16(sb + SM_ES + r1 * 32 + q * 8 + 2, cvt_bf16(b1 ? sbv[2] : sa[2]));
                sts16(sb + SM_ES + r1 * 32 + q * 8 + 6, cvt_bf16(b1 ? sbv[3] : sa[3]));
            }
            __syncwarp();
            if (lane == 0) mbar_arrive(bars + 8 * (BAR_STAGE + 0));
            if (ht == 0) TSTAMP(21);
            if (has_samples) {
                named_sync(4, 96);
#pragma unroll 1
                for (int s = 0; s < kNumStages - 1; s++) {
                    mbar_wait(bars + 8 * (BAR_GO + s), 0);
                    const uint32_t base = kPendMark | ((uint32_t)s << 19);
#pragma unroll 2
                    for (int i = ht; i < kLookups / 4; i += 96) {
                        const uint32_t sa = sb + SM_LK + i * 16;
                        const uint4 v = lds128(sa);
                        const uint32_t w[4] = {v.x - base, v.y - base, v.z - base, v.w - base};
#pragma unroll
                        for (int k = 0; k < 4; k++)
                            if (w[k] < 0x80000u)
                                asm volatile("cp.async.ca.shared.global [%0], [%1], 4;" ::"r"(sa + 4 * k), "l"(g_table + w[k]) : "memory");
                    }
                    asm volatile("cp.async.wait_all;" ::: "memory");
                    if (ht == 0) TSTAMP(22 + s);
                }
                __syncwarp();
                if (lane == 0) mbar_arrive(bars + 8 * BAR_GDONE);
            }
        }
    }
}

}

extern "C" void kernel_launch(void* const* d_in, const int* in_sizes, int n_in, void* d_out, int out_size) {
    (void)in_sizes; (void)n_in; (void)out_size;
    static bool attr_set = false;
    if (!attr_set) {
        cudaFuncSetAttribute(afm_kernel, cudaFuncAttributeMaxDynamicSharedMemorySize, SM_TOTAL + 1024);
        attr_set = true;
    }
    afm_kernel<<<kCTAs, kThreads, SM_TOTAL + 1024>>>(
        (const int*)d_in[0], (const __nv_bfloat16*)d_in[1], (const int*)d_in[2], (const int*)d_in[3],
        (const __nv_bfloat16*)d_in[4], (const __nv_bfloat16*)d_in[5], (const __nv_bfloat16*)d_in[6],
        (const __nv_bfloat16*)d_in[7], (__nv_bfloat16*)d_out);
}
```

```cpp
#include <cuda_runtime.h>
#include <cuda_bf16.h>
#include <stdint.h>

namespace {

constexpr int kD = 128, kB = 4096, kF = 26, kP = 325;
constexpr int kBlocks = 63;
constexpr int kSteps = 32;
constexpr int kMmaCTAs = 2 * kBlocks;
constexpr int kCTAs = 128;
constexpr int kSamplesPerCTA = kB / kCTAs;
constexpr int kPPad = 328;
constexpr int kThreads = 384;

constexpr int kMargin = 1;
constexpr int kFinalBins = 3;
constexpr uint32_t kStageMask = 0x2AAAA000u;
constexpr int popc32(uint32_t m) { return m ? (int)(m & 1) + popc32(m >> 1) : 0; }
constexpr int kNumStages = popc32(kStageMask);
static_assert((kStageMask >> (kSteps - kFinalBins - 1 + kMargin)) == 1, "the last trigger covers the last helper bin");
constexpr int kBinCap = 224;
constexpr int kBinBytes = kBinCap * 4;
constexpr int kGrpBytes = kSteps * kBinBytes + 128;
constexpr int kNumTuGroups = 4;

constexpr uint32_t kPend = 0x80000000u;
constexpr uint32_t kWrap = (uint32_t)kBlocks << 16;

constexpr int SM_W = 0;
constexpr int SM_H = SM_W + 49152;
constexpr int SM_TV = SM_H + 2048;
constexpr int SM_TU = SM_TV + 4096;
constexpr int SM_BIN = SM_TU + kSteps * 2048;
constexpr int SM_CNT = SM_BIN + 2 * kGrpBytes;
constexpr int SM_VAL = SM_CNT + 256;
constexpr int SM_FG = SM_VAL + kSamplesPerCTA * kPPad * 4;
constexpr int SM_IJ = SM_FG + kSamplesPerCTA * kF * 8;
constexpr int SM_B = SM_IJ + 352 * 4;
constexpr int SM_EP = SM_B + 256;
constexpr int SM_BAR = SM_EP + 16;
constexpr int SM_TOTAL = SM_BAR + 256;
static_assert(SM_TOTAL + 1024 <= 232448, "smem");
static_assert(SM_BAR % 8 == 0 && SM_VAL % 16 == 0 && SM_CNT % 128 == 0 && SM_FG % 16 == 0, "align");

constexpr int BAR_TU = 0;
constexpr int BAR_STAGE = BAR_TU + kNumTuGroups;
constexpr int BAR_EP = BAR_STAGE + kNumStages;
constexpr int BAR_LK = BAR_EP + 1;
constexpr int BAR_COUNT = BAR_LK + 1;
static_assert(BAR_COUNT * 8 <= 256, "bars");

constexpr uint32_t kSpinLimit = 1u << 22;

constexpr uint32_t kPadVal = 0x0000FF80u;
constexpr uint32_t kTag = 0x10000u;

__device__ uint32_t g_table[kSteps << 14];
__device__ uint32_t g_ticket;

__device__ __forceinline__ uint32_t smem_u32(const void* p) { return (uint32_t)__cvta_generic_to_shared(p); }

__device__ __forceinline__ void mbar_init(uint32_t bar, uint32_t cnt) {
    asm volatile("mbarrier.init.shared::cta.b64 [%0], %1;" ::"r"(bar), "r"(cnt) : "memory");
}
__device__ __forceinline__ void mbar_arrive(uint32_t bar) {
    asm volatile("mbarrier.arrive.shared::cta.b64 _, [%0];" ::"r"(bar) : "memory");
}
__device__ __forceinline__ void mbar_expect_tx(uint32_t bar, uint32_t bytes) {
    asm volatile("mbarrier.arrive.expect_tx.shared::cta.b64 _, [%0], %1;" ::"r"(bar), "r"(bytes) : "memory");
}
__device__ __forceinline__ bool mbar_try(uint32_t bar, uint32_t parity) {
    uint32_t ok;
    asm volatile("{\n\t.reg .pred p;\n\tmbarrier.try_wait.parity.shared::cta.b64 p, [%1], %2;\n\tselp.u32 %0, 1, 0, p;\n\t}"
                 : "=r"(ok) : "r"(bar), "r"(parity) : "memory");
    return ok != 0;
}
__device__ __forceinline__ void mbar_wait(uint32_t bar, uint32_t parity) {
    uint32_t n = 0;
    while (!mbar_try(bar, parity)) {
        if (++n > kSpinLimit) __trap();
    }
}
__device__ __forceinline__ void bulk_g2s(uint32_t dst, const void* src, uint32_t bytes, uint32_t bar) {
    asm volatile("cp.async.bulk.shared::cluster.global.mbarrier::complete_tx::bytes [%0], [%1], %2, [%3];"
                 ::"r"(dst), "l"(src), "r"(bytes), "r"(bar) : "memory");
}
__device__ __forceinline__ void cp_async16(uint32_t dst, const void* src) {
    asm volatile("cp.async.cg.shared.global [%0], [%1], 16;" ::"r"(dst), "l"(src) : "memory");
}
__device__ __forceinline__ uint4 lds128(uint32_t a) {
    uint4 v;
    asm volatile("ld.shared.v4.u32 {%0,%1,%2,%3}, [%4];" : "=r"(v.x), "=r"(v.y), "=r"(v.z), "=r"(v.w) : "r"(a));
    return v;
}
__device__ __forceinline__ uint32_t lds32(uint32_t a) {
    uint32_t v;
    asm volatile("ld.shared.u32 %0, [%1];" : "=r"(v) : "r"(a));
    return v;
}
__device__ __forceinline__ void sts32(uint32_t a, uint32_t v) { asm volatile("st.shared.u32 [%0], %1;" ::"r"(a), "r"(v) : "memory"); }
__device__ __forceinline__ uint32_t bmul2(uint32_t a, uint32_t b) {
    uint32_t d;
    asm("mul.rn.bf16x2 %0, %1, %2;" : "=r"(d) : "r"(a), "r"(b));
    return d;
}
__device__ __forceinline__ uint32_t pack_bf16x2(float hi, float lo) {
    uint32_t d;
    asm("cvt.rn.bf16x2.f32 %0, %1, %2;" : "=r"(d) : "f"(hi), "f"(lo));
    return d;
}
__device__ __forceinline__ uint32_t add_relu_bf16x2(uint32_t x, uint32_t b) {
    uint32_t d;
    asm("fma.rn.relu.bf16x2 %0, %1, %2, %3;" : "=r"(d) : "r"(x), "r"(0x3F803F80u), "r"(b));
    return d;
}
__device__ __forceinline__ void named_sync(int id, int n) { asm volatile("bar.sync %0, %1;" ::"r"(id), "r"(n) : "memory"); }
__device__ __forceinline__ void named_arrive(int id, int n) { asm volatile("bar.arrive %0, %1;" ::"r"(id), "r"(n) : "memory"); }

__device__ __forceinline__ void wgmma_m64n136k16(float (&d)[68], uint32_t a0, uint32_t a1, uint32_t a2, uint32_t a3,
                                                 uint64_t desc, int scale_d) {
    asm volatile(
        "{\n\t.reg .pred p;\n\tsetp.ne.b32 p, %73, 0;\n\t"
        "wgmma.mma_async.sync.aligned.m64n136k16.f32.bf16.bf16 "
        "{%0,%1,%2,%3,%4,%5,%6,%7,%8,%9,%10,%11,%12,%13,%14,%15,%16,%17,%18,%19,%20,%21,%22,%23,%24,%25,%26,%27,%28,%29,%30,%31,%32,%33,%34,%35,%36,%37,%38,%39,%40,%41,%42,%43,%44,%45,%46,%47,%48,%49,%50,%51,%52,%53,%54,%55,%56,%57,%58,%59,%60,%61,%62,%63,%64,%65,%66,%67},"
        "{%68,%69,%70,%71}, %72, p, 1, 1, 1;\n\t}"
        : "+f"(d[0]), "+f"(d[1]), "+f"(d[2]), "+f"(d[3]), "+f"(d[4]), "+f"(d[5]), "+f"(d[6]), "+f"(d[7]), "+f"(d[8]), "+f"(d[9]), "+f"(d[10]), "+f"(d[11]), "+f"(d[12]), "+f"(d[13]), "+f"(d[14]), "+f"(d[15]), "+f"(d[16]), "+f"(d[17]), "+f"(d[18]), "+f"(d[19]), "+f"(d[20]), "+f"(d[21]), "+f"(d[22]), "+f"(d[23]), "+f"(d[24]), "+f"(d[25]), "+f"(d[26]), "+f"(d[27]), "+f"(d[28]), "+f"(d[29]), "+f"(d[30]), "+f"(d[31]), "+f"(d[32]), "+f"(d[33]), "+f"(d[34]), "+f"(d[35]), "+f"(d[36]), "+f"(d[37]), "+f"(d[38]), "+f"(d[39]), "+f"(d[40]), "+f"(d[41]), "+f"(d[42]), "+f"(d[43]), "+f"(d[44]), "+f"(d[45]), "+f"(d[46]), "+f"(d[47]), "+f"(d[48]), "+f"(d[49]), "+f"(d[50]), "+f"(d[51]), "+f"(d[52]), "+f"(d[53]), "+f"(d[54]), "+f"(d[55]), "+f"(d[56]), "+f"(d[57]), "+f"(d[58]), "+f"(d[59]), "+f"(d[60]), "+f"(d[61]), "+f"(d[62]), "+f"(d[63]), "+f"(d[64]), "+f"(d[65]), "+f"(d[66]), "+f"(d[67])
        : "r"(a0), "r"(a1), "r"(a2), "r"(a3), "l"(desc), "r"(scale_d));
}
__device__ __forceinline__ void wgmma_m64n8k16(float (&d)[4], uint32_t a0, uint32_t a1, uint32_t a2, uint32_t a3,
                                               uint64_t desc, int scale_d) {
    asm volatile(
        "{\n\t.reg .pred p;\n\tsetp.ne.b32 p, %9, 0;\n\t"
        "wgmma.mma_async.sync.aligned.m64n8k16.f32.bf16.bf16 {%0,%1,%2,%3}, {%4,%5,%6,%7}, %8, p, 1, 1, 0;\n\t}"
        : "+f"(d[0]), "+f"(d[1]), "+f"(d[2]), "+f"(d[3])
        : "r"(a0), "r"(a1), "r"(a2), "r"(a3), "l"(desc), "r"(scale_d));
}
#define FENCE_R(arr, n) _Pragma("unroll") for (int _i = 0; _i < n; _i++) asm volatile("" : "+r"(arr[_i])::"memory")
#define FENCE_F(arr, n) _Pragma("unroll") for (int _i = 0; _i < n; _i++) asm volatile("" : "+f"(arr[_i])::"memory")

__device__ __forceinline__ uint32_t ld_table(uint32_t word) {
    uint32_t v;
    asm volatile("ld.relaxed.gpu.global.u32 %0, [%1];" : "=r"(v) : "l"(g_table + word) : "memory");
    return v;
}
__device__ __forceinline__ uint32_t lookup_word(uint32_t fx, uint32_t gx, uint32_t fy, uint32_t gy) {
    const uint32_t w1 = fx + gy, w2 = fy + gx;
    const int w = min(__viaddmin_s32((int)w1, (int)kWrap, (int)w2), __viaddmin_s32((int)w2, (int)kWrap, (int)w1));
    return (uint32_t)__viaddmin_s32(w, -(31 << 16), w);
}

__device__ __forceinline__ void wait_probe(const uint32_t* p, uint32_t tag) {
    for (uint32_t n = 0;; n++) {
        uint32_t v;
        asm volatile("ld.relaxed.gpu.global.u32 %0, [%1];" : "=r"(v) : "l"(p) : "memory");
        if (!((v ^ tag) & kTag)) break;
        if (n > kSpinLimit) __trap();
        __nanosleep(100);
    }
}

__device__ __forceinline__ void make_pairs(uint32_t (&a)[32], const uint32_t (&tv0)[16], const uint32_t (&tv1)[16], uint32_t addr) {
#pragma unroll
    for (int j = 0; j < 4; j++) {
        const uint4 u = lds128(addr + 64 * j);
        a[8 * j + 0] = bmul2(tv0[4 * j + 0], u.x); a[8 * j + 1] = bmul2(tv1[4 * j + 0], u.x);
        a[8 * j + 2] = bmul2(tv0[4 * j + 1], u.y); a[8 * j + 3] = bmul2(tv1[4 * j + 1], u.y);
        a[8 * j + 4] = bmul2(tv0[4 * j + 2], u.z); a[8 * j + 5] = bmul2(tv1[4 * j + 2], u.z);
        a[8 * j + 6] = bmul2(tv0[4 * j + 3], u.w); a[8 * j + 7] = bmul2(tv1[4 * j + 3], u.w);
    }
}

template <bool kMore>
__device__ __forceinline__ void consumer_step(float (&acc)[68], uint32_t (&X)[32], uint32_t (&Y)[32], const uint32_t (&tv0)[16],
                                              const uint32_t (&tv1)[16], const uint32_t (&bpk)[16], uint64_t descw, uint64_t desch,
                                              uint32_t& tu_addr, uint32_t*& e_ptr, uint32_t& stage_bar, uint32_t tag, int t, int wg,
                                              int lane) {
    named_sync(2 + wg, 256);
    asm volatile("wgmma.wait_group.sync.aligned 0;" ::: "memory");
    FENCE_F(acc, 68);
    FENCE_R(X, 32);
#pragma unroll
    for (int j = 0; j < 8; j++) {
        X[4 * j + 0] = add_relu_bf16x2(pack_bf16x2(acc[8 * j + 1], acc[8 * j + 0]), bpk[2 * j]);
        X[4 * j + 1] = add_relu_bf16x2(pack_bf16x2(acc[8 * j + 3], acc[8 * j + 2]), bpk[2 * j]);
        X[4 * j + 2] = add_relu_bf16x2(pack_bf16x2(acc[8 * j + 5], acc[8 * j + 4]), bpk[2 * j + 1]);
        X[4 * j + 3] = add_relu_bf16x2(pack_bf16x2(acc[8 * j + 7], acc[8 * j + 6]), bpk[2 * j + 1]);
    }
    float sv = (lane & 2) ? acc[66] : acc[64];
    float ed[4];
    asm volatile("" : "+f"(sv)::"memory");
    FENCE_R(X, 32);
    asm volatile("wgmma.fence.sync.aligned;" ::: "memory");
#pragma unroll
    for (int s = 0; s < 8; s++)
        wgmma_m64n8k16(ed, X[4 * s], X[4 * s + 1], X[4 * s + 2], X[4 * s + 3], desch + (uint64_t)(s * 16), s);
    asm volatile("wgmma.commit_group.sync.aligned;" ::: "memory");
    if (kMore) {
#pragma unroll
        for (int s = 0; s < 8; s++)
            wgmma_m64n136k16(acc, Y[4 * s], Y[4 * s + 1], Y[4 * s + 2], Y[4 * s + 3], descw + (uint64_t)(s * 128), s);
        asm volatile("wgmma.commit_group.sync.aligned;" ::: "memory");
        named_arrive(3 - wg, 256);
        asm volatile("wgmma.wait_group.sync.aligned 1;" ::: "memory");
    } else {
        if (wg == 0) named_arrive(3, 256);
        asm volatile("wgmma.wait_group.sync.aligned 0;" ::: "memory");
    }
    FENCE_F(ed, 4);
    FENCE_R(X, 32);
    if (!(lane & 1))
        asm volatile("st.global.u32 [%0], %1;" ::"l"(e_ptr), "r"((pack_bf16x2(sv, (lane & 2) ? ed[2] : ed[0]) & ~kTag) | tag) : "memory");
    e_ptr += 1 << 14;
    if ((kStageMask >> t) & 1) {
        __syncwarp();
        if (lane == 0) mbar_arrive(stage_bar);
        stage_bar += 8;
    }
    if (kMore) {
        make_pairs(X, tv0, tv1, tu_addr);
        tu_addr += 2048;
        FENCE_R(X, 32);
    }
}

__global__ void __launch_bounds__(kThreads, 1)
afm_kernel(const int* __restrict__ idx, const __nv_bfloat16* __restrict__ table, const int* __restrict__ ii,
           const int* __restrict__ jj, const __nv_bfloat16* __restrict__ W, const __nv_bfloat16* __restrict__ bias,
           const __nv_bfloat16* __restrict__ hvec, const __nv_bfloat16* __restrict__ pvec,
           __nv_bfloat16* __restrict__ out) {
    extern __shared__ uint8_t smem_raw[];
    const uint32_t sb = (smem_u32(smem_raw) + 1023u) & ~1023u;
    const int tid = threadIdx.x, warp = tid >> 5, lane = tid & 31;
    const int g = lane >> 2, q = lane & 3;
    const int cta = blockIdx.x;
    const int J = cta >> 1, half = cta & 1;
    const bool has_mma = cta < kMmaCTAs;
    const uint32_t bars = sb + SM_BAR;
    const int t_skip = !half ? -1 : J == kBlocks - 1 ? kSteps - 1 : kBlocks - 2 - J >= kSteps - 1 ? -1 : kBlocks - 2 - J;
    auto load_tu = [&](int t, int grp) {
        int blk = t == kSteps - 1 ? J : J + t + 1;
        if (blk >= kBlocks) blk -= kBlocks;
        if (t != t_skip)
            bulk_g2s(sb + SM_TU + t * 2048, table + (size_t)(blk * 16 + half * 8) * kD, 2048, bars + 8 * (BAR_TU + grp));
    };

    uint4 hchunk = make_uint4(0, 0, 0, 0);
    uint32_t ticket = 0;
    if (warp < 8) {
        if (has_mma) {
#pragma unroll
            for (int i = 0; i < 8; i++) {
                const int ch = tid + 256 * i;
                const int d = ch >> 4, cc = ch & 15;
                const int kap = (d & ~31) + ((d >> 2) & 1) * 16 + ((d >> 1) & 1) * 8 + ((d >> 3) & 3) * 2 + (d & 1);
                const uint32_t dst = sb + SM_W + (cc >> 3) * 16384 + (kap >> 3) * 1024 + (kap & 7) * 128 + (((cc & 7) ^ (kap & 7)) << 4);
                cp_async16(dst, W + d * kD + cc * 8);
            }
            if (tid < 128) hchunk = __ldg(reinterpret_cast<const uint4*>(hvec) + (tid >> 3));
            else hchunk.x = __ldg(reinterpret_cast<const uint16_t*>(pvec) + tid - 128);
            if (tid < 16) cp_async16(sb + SM_B + tid * 16, bias + tid * 8);
            asm volatile("cp.async.commit_group;" ::: "memory");
        }
    } else if (tid == 288) {
        asm volatile("atom.relaxed.gpu.global.add.u32 %0, [%1], 1;" : "=r"(ticket) : "l"(&g_ticket) : "memory");
    } else if (tid == 256) {
        for (int i = 0; i < kNumTuGroups; i++) mbar_init(bars + 8 * (BAR_TU + i), 1);
        for (int i = 0; i < kNumStages; i++) mbar_init(bars + 8 * (BAR_STAGE + i), 8);
        mbar_init(bars + 8 * BAR_EP, 1);
        mbar_init(bars + 8 * BAR_LK, 4);
        asm volatile("fence.mbarrier_init.release.cluster;" ::: "memory");
        asm volatile("fence.proxy.async.shared::cta;" ::: "memory");
        if (has_mma) {
            const uint32_t tv_bytes = J == kBlocks - 1 ? 2048 : 4096;
            mbar_expect_tx(bars + 8 * (BAR_TU + 0), tv_bytes + (t_skip == 0 || t_skip == 1 ? 2048 : 4096));
            bulk_g2s(sb + SM_TV, table + (size_t)J * 16 * kD, tv_bytes, bars + 8 * BAR_TU);
            load_tu(0, 0);
            load_tu(1, 0);
            mbar_expect_tx(bars + 8 * (BAR_TU + 1), (t_skip >= 2 && t_skip < 8 ? 5 : 6) * 2048);
            mbar_expect_tx(bars + 8 * (BAR_TU + 2), (t_skip >= 8 && t_skip < 16 ? 7 : 8) * 2048);
            mbar_expect_tx(bars + 8 * (BAR_TU + 3), (t_skip >= 16 && t_skip < 32 ? 15 : 16) * 2048);
        }
    }
    __syncthreads();

    if (warp < 8) {
        asm volatile("setmaxnreg.inc.sync.aligned.u32 216;");
        if (has_mma) {
            const int wg = warp >> 2;
            uint32_t bpk[16], tv0[16], tv1[16], X[32], Y[32];
            float acc[68];
            mbar_wait(bars + 8 * BAR_TU, 0);
#pragma unroll
            for (int j = 0; j < 4; j++) {
                uint4 v = lds128(sb + SM_TV + g * 256 + q * 16 + 64 * j);
                tv0[4 * j] = v.x; tv0[4 * j + 1] = v.y; tv0[4 * j + 2] = v.z; tv0[4 * j + 3] = v.w;
                v = lds128(sb + SM_TV + 2048 + g * 256 + q * 16 + 64 * j);
                tv1[4 * j] = v.x; tv1[4 * j + 1] = v.y; tv1[4 * j + 2] = v.z; tv1[4 * j + 3] = v.w;
            }
            uint32_t tu_addr = sb + SM_TU + warp * 256 + q * 16;

            uint32_t stage_bar = bars + 8 * BAR_STAGE;
            make_pairs(X, tv0, tv1, tu_addr);
            make_pairs(Y, tv0, tv1, tu_addr + 2048);
            tu_addr += 4096;
            {
                const int d = tid - 128;
                const int kap = (d & ~31) + ((d >> 2) & 1) * 16 + ((d >> 1) & 1) * 8 + ((d >> 3) & 3) * 2 + (d & 1);
                if (tid >= 128) hchunk.x = hchunk.y = hchunk.z = hchunk.w = hchunk.x * 0x10001u;
                asm volatile("st.shared.v4.u32 [%0], {%1,%2,%3,%4};"
                             ::"r"(tid < 128 ? sb + SM_H + tid * 16 : sb + SM_W + 32768 + (kap >> 3) * 1024 + (kap & 7) * 144),
                             "r"(hchunk.x), "r"(hchunk.y), "r"(hchunk.z), "r"(hchunk.w) : "memory");
            }
            asm volatile("cp.async.wait_group 0;" ::: "memory");
            asm volatile("fence.proxy.async.shared::cta;" ::: "memory");
            named_sync(1, 256);
            named_arrive(5, 288);
#pragma unroll
            for (int j = 0; j < 16; j++) bpk[j] = lds32(sb + SM_B + 16 * j + 4 * q);
            const uint64_t descw = (uint64_t)(((sb + SM_W) & 0x3FFFF) >> 4) | ((uint64_t)(16384 >> 4) << 16) |
                                   ((uint64_t)(1024 >> 4) << 32) | (1ull << 62);
            const uint64_t desch = (uint64_t)(((sb + SM_H) & 0x3FFFF) >> 4) | ((uint64_t)(128 >> 4) << 16) | ((uint64_t)(256 >> 4) << 32);
            uint32_t* es_addr = g_table + (cta << 7) + warp * 16 + g + 8 * (q >> 1);
            if (wg == 1) named_sync(3, 256);
            FENCE_R(X, 32);
            asm volatile("wgmma.fence.sync.aligned;" ::: "memory");
#pragma unroll
            for (int s = 0; s < 8; s++)
                wgmma_m64n136k16(acc, X[4 * s], X[4 * s + 1], X[4 * s + 2], X[4 * s + 3], descw + (uint64_t)(s * 128), s);
            asm volatile("wgmma.commit_group.sync.aligned;" ::: "memory");
            named_arrive(3 - wg, 256);
            mbar_wait(bars + 8 * BAR_EP, 0);
            const uint32_t tag = lds32(sb + SM_EP);
#pragma unroll 1
            for (int t = 0; t < kSteps - 2; t += 2) {
                if (t == 0) mbar_wait(bars + 8 * (BAR_TU + 1), 0);
                if (t == 6) mbar_wait(bars + 8 * (BAR_TU + 2), 0);
                if (t == 14) mbar_wait(bars + 8 * (BAR_TU + 3), 0);
                consumer_step<true>(acc, X, Y, tv0, tv1, bpk, descw, desch, tu_addr, es_addr, stage_bar, tag, t, wg, lane);
                consumer_step<true>(acc, Y, X, tv0, tv1, bpk, descw, desch, tu_addr, es_addr, stage_bar, tag, t + 1, wg, lane);
            }
            consumer_step<true>(acc, X, Y, tv0, tv1, bpk, descw, desch, tu_addr, es_addr, stage_bar, tag, kSteps - 2, wg, lane);
            consumer_step<false>(acc, Y, X, tv0, tv1, bpk, descw, desch, tu_addr, es_addr, stage_bar, tag, kSteps - 1, wg, lane);
        }
        mbar_wait(bars + 8 * BAR_EP, 0);
        const uint32_t tag = lds32(sb + SM_EP);
        if (!has_mma) wait_probe(g_table + ((kSteps - 1) << 14), tag);
        mbar_wait(bars + 8 * BAR_LK, 0);
        {
            const int grp = warp >> 2;
            uint32_t ent[2 * kFinalBins], got[2 * kFinalBins];
#pragma unroll
            for (int k = 0; k < 2 * kFinalBins; k++) {
                const uint32_t bin = sb + SM_BIN + grp * kGrpBytes + (kSteps - kFinalBins + (k >> 1)) * kBinBytes;
                const uint32_t end = min(lds32(sb + SM_CNT + (grp * kSteps + kSteps - kFinalBins + (k >> 1)) * 4), bin + kBinBytes);
                const uint32_t src = bin + ((warp & 3) + 4 * (k & 1)) * 128 + lane * 4;
                ent[k] = lds32(src);
                got[k] = src < end ? tag ^ kTag : tag;
                if (src >= end) ent[k] = 0x1FFF;
            }
#pragma unroll 1
            for (uint32_t n = 0;; n++) {
                uint32_t missing = 0;
#pragma unroll
                for (int k = 0; k < 2 * kFinalBins; k++)
                    if ((got[k] ^ tag) & kTag) got[k] = ld_table(ent[k] >> 13);
#pragma unroll
                for (int k = 0; k < 2 * kFinalBins; k++) missing |= got[k] ^ tag;
                if (!__any_sync(0xffffffffu, missing & kTag)) break;
                if (n > kSpinLimit) __trap();
            }
#pragma unroll
            for (int k = 0; k < 2 * kFinalBins; k++)
                if (ent[k] != 0x1FFF) sts32(sb + SM_VAL + grp * 16 * kPPad * 4 + (ent[k] & 0x1FFF) * 4, got[k]);
            named_sync(6 + grp, 192);
        }
        uint32_t val[4][12];
#pragma unroll 1
        for (int n = 0; n < 2; n++) {
            uint32_t missing = 0;
#pragma unroll
            for (int sidx = 0; sidx < 4; sidx++)
#pragma unroll
                for (int i = 0; i < 3; i++) {
                    uint4 v = make_uint4(kPadVal | tag, kPadVal | tag, kPadVal | tag, kPadVal | tag);
                    if (i < 2 || lane < (kPPad - 256) / 4) v = lds128(sb + SM_VAL + (warp * 4 + sidx) * kPPad * 4 + i * 512 + lane * 16);
                    val[sidx][4 * i] = v.x; val[sidx][4 * i + 1] = v.y; val[sidx][4 * i + 2] = v.z; val[sidx][4 * i + 3] = v.w;
                    missing |= (v.x ^ tag) | (v.y ^ tag);
                    missing |= (v.z ^ tag) | (v.w ^ tag);
                }
            if (!__any_sync(0xffffffffu, missing & kTag)) break;
#pragma unroll 1
            for (int k = lane; k < 4 * kPPad; k += 32) {
                const uint32_t dst = sb + SM_VAL + (warp * 4 * kPPad + k) * 4;
                uint32_t v = lds32(dst);
                if ((v ^ tag) & kTag) {
                    const uint32_t ij = lds32(sb + SM_IJ + (k % kPPad) * 4);
                    const uint32_t fg = sb + SM_FG + (warp * 4 + k / kPPad) * kF * 8;
                    const uint32_t oi = fg + (ij & 0xFFFF), oj = fg + (ij >> 16);
                    const uint32_t w = lookup_word(lds32(oi), lds32(oi + 4), lds32(oj), lds32(oj + 4));
                    for (uint32_t m = 0; (v ^ tag) & kTag; m++) {
                        v = ld_table((w - kPend) >> 2);
                        if (m > kSpinLimit) __trap();
                    }
                    sts32(dst, v);
                }
            }
            __syncwarp();
        }
        float red[8];
#pragma unroll
        for (int sidx = 0; sidx < 4; sidx++) {
            uint32_t m2 = val[sidx][0];
#pragma unroll
            for (int i = 1; i < 12; i++) asm("max.bf16x2 %0, %0, %1;" : "+r"(m2) : "r"(val[sidx][i]));
            int key = (int)(m2 << 16);
            key ^= (key >> 31) & 0x7FFF0000;
            key = __reduce_max_sync(0xffffffffu, key);
            key ^= (key >> 31) & 0x7FFF0000;
            const float ml = __int_as_float(key) * 1.4426950408889634f;
            float l = 0.f, a = 0.f;
#pragma unroll
            for (int i = 0; i < 12; i++) {
                float w;
                asm("ex2.approx.ftz.f32 %0, %1;" : "=f"(w) : "f"(fmaf(__uint_as_float(val[sidx][i] << 16), 1.4426950408889634f, -ml)));
                l += w;
                a = fmaf(w, __uint_as_float((val[sidx][i] & 0xFFFE0000u) | 0x8000u), a);
            }
            red[2 * sidx] = l;
            red[2 * sidx + 1] = a;
        }
#pragma unroll
        for (int k = 0; k < 4; k++) {
            const bool up = lane & 16;
            const float send = up ? red[k] : red[k + 4], keep = up ? red[k + 4] : red[k];
            red[k] = keep + __shfl_xor_sync(0xffffffffu, send, 16);
        }
#pragma unroll
        for (int k = 0; k < 2; k++) {
            const bool up = lane & 8;
            const float send = up ? red[k] : red[k + 2], keep = up ? red[k + 2] : red[k];
            red[k] = keep + __shfl_xor_sync(0xffffffffu, send, 8);
        }
#pragma unroll
        for (int o = 4; o > 0; o >>= 1) {
            red[0] += __shfl_xor_sync(0xffffffffu, red[0], o);
            red[1] += __shfl_xor_sync(0xffffffffu, red[1], o);
        }
        if ((lane & 7) == 0) out[cta * kSamplesPerCTA + warp * 4 + (lane >> 3)] = __float2bfloat16(red[1] / red[0]);
    } else {
        asm volatile("setmaxnreg.dec.sync.aligned.u32 72;");
        const int hw = warp - 8;
        if (has_mma && lane == 0) {
            load_tu(2 + hw, 1);
            if (hw < 2) load_tu(6 + hw, 1);
        }
        if (tid == 288) {
            sts32(sb + SM_EP, (~ticket / kCTAs & 1) * kTag);
            mbar_arrive(bars + 8 * BAR_EP);
        }
        int id[7], fi[3], fj[3];
#pragma unroll
        for (int k = 0; k < 7; k++) {
            const int i = lane + 32 * k;
            id[k] = i < 8 * kF ? __ldg(idx + (cta * kSamplesPerCTA + hw * 8) * kF + i) : 0;
        }
#pragma unroll
        for (int k = 0; k < 3; k++) {
            const int p = tid - 256 + 128 * k;
            fi[k] = p < kP ? __ldg(ii + p) : 0;
            fj[k] = p < kP ? __ldg(jj + p) : 0;
        }
#pragma unroll
        for (int k = 0; k < 7; k++) {
            const int i = lane + 32 * k;
            const uint32_t blk = (uint32_t)id[k] >> 4, lo = (uint32_t)id[k] & 15;
            const uint32_t f = kPend - (1u << 16) + (blk << 10) + (lo << 2) - (blk << 16), gg = (blk << 16) + (lo << 6);
            if (i < 8 * kF) asm volatile("st.shared.v2.u32 [%0], {%1,%2};" ::"r"(sb + SM_FG + (hw * 8 * kF + i) * 8), "r"(f), "r"(gg) : "memory");
        }
#pragma unroll
        for (int k = 0; k < 3; k++) {
            const int p = tid - 256 + 128 * k;
            if (p < 352) sts32(sb + SM_IJ + p * 4, (uint32_t)fi[k] * 8 | (uint32_t)fj[k] * 8 << 16);
        }
        if (hw < 2) sts32(sb + SM_CNT + (hw * kSteps + lane) * 4, sb + SM_BIN + hw * kGrpBytes + lane * kBinBytes);
        mbar_wait(bars + 8 * BAR_EP, 0);
        const uint32_t tag = lds32(sb + SM_EP);
#pragma unroll
        for (int k = 0; k < 21; k++) {
            const int i = lane + 32 * k;
            if (i < 8 * kPPad / 4)
                asm volatile("st.shared.v4.u32 [%0], {%1,%1,%1,%1};" ::"r"(sb + SM_VAL + (hw * 8 * kPPad / 4 + i) * 16), "r"(tag ^ kTag) : "memory");
        }
        named_sync(4, 128);
        if (has_mma) {
            if (hw == 3) {
                named_sync(5, 288);
                if (lane == 0) {
#pragma unroll 1
                    for (int t = 8; t < kSteps; t++) load_tu(t, t < 16 ? 2 : 3);
                }
            }
        }
        const int grp = hw >> 1;
        const uint32_t cnt = sb + SM_CNT + grp * 128, bin_end = sb + SM_BIN + grp * kGrpBytes + kSteps * kBinBytes;
        if (lane < 24) sts32(sb + SM_VAL + ((hw * 8 + lane / 3) * kPPad + kP + lane % 3) * 4, kPadVal | tag);
#pragma unroll 1
        for (int i = 0; i < 11; i++) {
            const uint32_t ij = lds32(sb + SM_IJ + (lane + 32 * i) * 4);
            const uint32_t oi = sb + SM_FG + hw * 8 * kF * 8 + (ij & 0xFFFF), oj = sb + SM_FG + hw * 8 * kF * 8 + (ij >> 16);
            const uint32_t slot = (hw & 1) * 8 * kPPad + lane + 32 * i;
            if (i < 10 || lane < kP - 320) {
                uint32_t fx[8], gx[8], fy[8], gy[8], pos[8];
#pragma unroll
                for (int sm = 0; sm < 8; sm++) {
                    asm volatile("ld.shared.v2.u32 {%0,%1}, [%2];" : "=r"(fx[sm]), "=r"(gx[sm]) : "r"(oi + sm * kF * 8));
                    asm volatile("ld.shared.v2.u32 {%0,%1}, [%2];" : "=r"(fy[sm]), "=r"(gy[sm]) : "r"(oj + sm * kF * 8));
                }
#pragma unroll
                for (int sm = 0; sm < 8; sm++) {
                    fx[sm] = lookup_word(fx[sm], gx[sm], fy[sm], gy[sm]);
                    asm volatile("atom.shared.add.u32 %0, [%1], 4;" : "=r"(pos[sm]) : "r"(((fx[sm] >> 14) & 0x7C) | cnt) : "memory");
                }
#pragma unroll
                for (int sm = 0; sm < 8; sm++) sts32(min(pos[sm], bin_end), fx[sm] * 2048 + (slot + sm * kPPad));
            }
        }
        named_sync(4, 128);
        if (lane == 0) mbar_arrive(bars + 8 * BAR_LK);
        const uint32_t my_end = min(lds32(cnt + lane * 4), sb + SM_BIN + grp * kGrpBytes + (lane + 1) * kBinBytes);
        const uint32_t vbase = sb + SM_VAL + grp * 16 * kPPad * 4;
        uint32_t src = sb + SM_BIN + grp * kGrpBytes + (hw & 1) * 128 + lane * 4;
        uint32_t mask = kStageMask, stage_bar = bars + 8 * BAR_STAGE;
        int t = 0;
#pragma unroll 1
        while (mask) {
            const int trig = __ffs(mask) - 1;
            mask &= mask - 1;
            if (has_mma) mbar_wait(stage_bar, 0);
            else wait_probe(g_table + (trig << 14), tag);
            stage_bar += 8;
#pragma unroll 1
            for (; t <= trig - kMargin; t++, src += kBinBytes) {
                const uint32_t end = __shfl_sync(0xffffffffu, my_end, t);
                uint32_t e[4];
#pragma unroll
                for (int k = 0; k < 4; k++) e[k] = lds32(src + k * 256);
#pragma unroll
                for (int k = 0; k < 4; k++)
                    if (src + k * 256 < end)
                        asm volatile("cp.async.ca.shared.global [%0], [%1], 4;"
                                     ::"r"(vbase + (e[k] & 0x1FFF) * 4), "l"(g_table + (e[k] >> 13)) : "memory");
            }
        }
        asm volatile("cp.async.wait_all;" ::: "memory");
        named_arrive(6 + grp, 192);
    }
}

}

extern "C" void kernel_launch(void* const* d_in, const int* in_sizes, int n_in, void* d_out, int out_size) {
    (void)in_sizes; (void)n_in; (void)out_size;
    static bool attr_set = false;
    if (!attr_set) {
        cudaFuncSetAttribute(afm_kernel, cudaFuncAttributeMaxDynamicSharedMemorySize, SM_TOTAL + 1024);
        attr_set = true;
    }
    afm_kernel<<<kCTAs, kThreads, SM_TOTAL + 1024>>>(
        (const int*)d_in[0], (const __nv_bfloat16*)d_in[1], (const int*)d_in[2], (const int*)d_in[3],
        (const __nv_bfloat16*)d_in[4], (const __nv_bfloat16*)d_in[5], (const __nv_bfloat16*)d_in[6],
        (const __nv_bfloat16*)d_in[7], (__nv_bfloat16*)d_out);
}
```
